```python
import torch

def _softmax(x, axis=-1):
    return torch.softmax(x, dim=axis)
def _gelu(x):
    return torch.nn.functional.gelu(x, approximate="tanh")
def _silu(x):
    return torch.nn.functional.silu(x)
def _sigmoid(x):
    return torch.sigmoid(x)
def _layernorm(x, axis=-1, eps=1e-5):
    m = x.mean(dim=axis, keepdim=True)
    v = x.var(dim=axis, keepdim=True, unbiased=False)
    return (x - m) / torch.sqrt(v + eps)
def _scatter_add(tgt, idx, src, axis=0):
    return tgt.clone().index_add_(axis, idx, src)
def _segment_sum(src, seg, n):
    out = torch.zeros((n,) + src.shape[1:], dtype=src.dtype)
    return out.index_add_(0, seg, src)
def _pad(x, pw):
    flat = tuple(v for pair in reversed(pw) for v in pair)
    return torch.nn.functional.pad(x, flat)

kernel_name = 'recurrent_scan__compressed_kv_cla__swiglu_ffn__prompt'

def setup_inputs():

    _w = (lambda a: (lambda t: t.to(torch.bfloat16) if t.is_floating_point() else t)(torch.as_tensor(a)))
    def _A_setup():
        B, H, Sq, Sk, D, M = 1, 16, 2048, 2048, 256, 448
        Dc = 4 * D
        return {
            "x": _w((lambda *s: torch.randn(*s, dtype=torch.bfloat16) * 0.05)(B, Sq, M)),
            "c_kv": _w((lambda *s: torch.randn(*s, dtype=torch.bfloat16) * 0.2)(B, Sk, Dc)),
            "w_q": _w((lambda *s: torch.randn(*s, dtype=torch.bfloat16) * 3.2)(M, H, D) * (M ** -0.5)),
            "w_uk": _w((lambda *s: torch.randn(*s, dtype=torch.bfloat16) * 3.2)(Dc, H, D) * (Dc ** -0.5)),
            "w_uv": _w((lambda *s: torch.randn(*s, dtype=torch.bfloat16) * 0.2)(Dc, H, D) * (Dc ** -0.5)),
            "w_o": _w((lambda *s: torch.randn(*s, dtype=torch.bfloat16) * 0.2)(H, D, M) * ((H * D) ** -0.5)),
        }
    _A_in = _A_setup()

    def _B_setup():
        B, S, D, F = 1, 2048, 448, 1792
        return {
            "x": _w((lambda *s: torch.randn(*s, dtype=torch.bfloat16) * 0.05)(B, S, D)),
            "w_gate": _w((lambda *s: torch.randn(*s, dtype=torch.bfloat16) * 0.1)(D, F)),
            "w_up": _w((lambda *s: torch.randn(*s, dtype=torch.bfloat16) * 0.1)(D, F)),
            "w_down": _w((lambda *s: torch.randn(*s, dtype=torch.bfloat16) * 0.1)(F, D)),
        }
    _B_in = _B_setup()

    return {
        "A_x": _A_in["x"],
        "A_c_kv": _A_in["c_kv"],
        "A_w_q": _A_in["w_q"],
        "A_w_uk": _A_in["w_uk"],
        "A_w_uv": _A_in["w_uv"],
        "A_w_o": _A_in["w_o"],
        "B_x": _B_in["x"],
        "B_w_gate": _B_in["w_gate"],
        "B_w_up": _B_in["w_up"],
        "B_w_down": _B_in["w_down"],
    }

def reference(A_x, A_c_kv, A_w_q, A_w_uk, A_w_uv, A_w_o, B_x, B_w_gate, B_w_up, B_w_down):
    def _A_ref(x, c_kv, w_q, w_uk, w_uv, w_o):
        B, Sq, M = x.shape[0], x.shape[1], x.shape[2]
        Sk = c_kv.shape[1]
        H, D = w_q.shape[1], w_q.shape[2]
        q = torch.einsum("bqm,mhd->bhqd", x, w_q)
        k = torch.einsum("bkc,chd->bhkd", c_kv, w_uk)
        v = torch.einsum("bkc,chd->bhkd", c_kv, w_uv)
        scores = torch.einsum("bhqd,bhkd->bhqk", q, k) * (D ** -0.5)
        off = Sk - Sq
        qi = torch.arange(Sq)[:, None]
        kj = torch.arange(Sk)[None, :]
        cmask = kj <= (qi + off)
        scores = torch.where(cmask[None, None], scores, -1e9)
        p = _softmax(scores, axis=-1)
        ctx = torch.einsum("bhqk,bhkd->bhqd", p, v)
        return torch.einsum("bhqd,hdm->bqm", ctx, w_o)

    def _B_ref(x, w_gate, w_up, w_down):
        g = _silu(x @ w_gate)
        u = x @ w_up
        return (g * u) @ w_down

    x = A_x
    xn = _layernorm(x, axis=-1)
    s = _A_ref(xn, A_c_kv, A_w_q, A_w_uk, A_w_uv, A_w_o)
    g = _silu(_B_ref(xn, B_w_gate, B_w_up, B_w_down))
    return x + s * g
```

```cpp
#include <cuda_runtime.h>
#include <cuda_bf16.h>
#include <cuda.h>
#include <stdint.h>

namespace {

constexpr int SEQ = 2048, DM = 448, DC = 1024, NH = 16, HD = 256, FF = 1792;
constexpr int NB = 5, NA = 4;
constexpr int B_SLOT = 32768, A_UNIT = 16384;
constexpr int SMEM_DATA = NA * A_UNIT + NB * B_SLOT;
constexpr int SMEM_BYTES = SMEM_DATA + 1024 + 512;
constexpr int MAX_CL = 66, MAX_ITEMS = 16;
constexpr int NV4 = 28;
constexpr int NCMB = NH / 2 + 2;
constexpr int NPART = NH + 8;
constexpr int KVW = 2 * NH * HD + 11 * 256;
constexpr unsigned SPIN_LIMIT = 1u << 24;
constexpr unsigned POLL_NS = 300;

enum { T_KV = 0, T_ATT = 1, T_FFN = 2, T_END = 3 };
enum { M_SINGLE = 0, M_PARK = 1, M_MERGE = 2 };

struct Params {
  CUtensorMap tm_ckv, tm_wuk, tm_wuv, tm_kv, tm_xn, tm_wq, tm_wg, tm_wu;
  CUtensorMap tm_proj[4];
  const __nv_bfloat16* x;
  __nv_bfloat16* out;
  uint16_t sched[MAX_CL][MAX_ITEMS];
};

__device__ __nv_bfloat16 g_kv[(size_t)SEQ * KVW];
__device__ __nv_bfloat16 g_xn[SEQ * DM];
__device__ uint4 g_part[NPART][32 * 4 * NV4 * 32];
__device__ unsigned g_kvflag[256 + 11 * 8];
__device__ unsigned g_pflag[32][32];
__device__ unsigned g_ln;
__device__ unsigned g_epoch;

__device__ __forceinline__ uint32_t smem_u32(const void* p) { return (uint32_t)__cvta_generic_to_shared(p); }
__device__ __forceinline__ void mbar_init(uint32_t bar, int cnt) { asm volatile("mbarrier.init.shared::cta.b64 [%0], %1;" :: "r"(bar), "r"(cnt)); }
__device__ __forceinline__ void mbar_expect_tx(uint32_t bar, uint32_t bytes) { asm volatile("mbarrier.arrive.expect_tx.shared::cta.b64 _, [%0], %1;" :: "r"(bar), "r"(bytes) : "memory"); }
__device__ __forceinline__ void mbar_arrive(uint32_t bar) { asm volatile("mbarrier.arrive.shared::cta.b64 _, [%0];" :: "r"(bar) : "memory"); }
__device__ __forceinline__ void mbar_arrive_rlx(uint32_t bar) { asm volatile("mbarrier.arrive.relaxed.cta.shared::cta.b64 _, [%0];" :: "r"(bar) : "memory"); }
__device__ __forceinline__ void mbar_arrive_cluster(uint32_t bar, uint32_t cta) {
  asm volatile("{\n.reg .b32 ra;\nmapa.shared::cluster.u32 ra, %0, %1;\nmbarrier.arrive.relaxed.cluster.shared::cluster.b64 _, [ra];\n}\n" :: "r"(bar), "r"(cta) : "memory");
}
__device__ __forceinline__ unsigned ld_relaxed(const unsigned* p) {
  unsigned v; asm volatile("ld.relaxed.gpu.global.u32 %0, [%1];" : "=r"(v) : "l"(p) : "memory"); return v;
}
__device__ __forceinline__ void mbar_wait(uint32_t bar, uint32_t parity) {
  asm volatile("{\n.reg .pred p, q;\n.reg .u32 n;\nmov.u32 n, 0;\n"
               "LAB_WAIT:\nmbarrier.try_wait.parity.shared::cta.b64 p, [%0], %1;\n"
               "add.u32 n, n, 1;\nsetp.lt.and.u32 q, n, 0x1000000, !p;\n@q bra LAB_WAIT;\n}\n"
               :: "r"(bar), "r"(parity) : "memory");
}
__device__ __forceinline__ void mbar_wait_bg(uint32_t bar, uint32_t parity) {
  asm volatile("{\n.reg .pred p;\n.reg .u32 n;\nmov.u32 n, 0;\n"
               "LAB_WAIT:\nmbarrier.try_wait.parity.shared::cta.b64 p, [%0], %1, 2000;\n@p bra LAB_DONE;\n"
               "nanosleep.u32 64;\n"
               "add.u32 n, n, 1;\nsetp.lt.u32 p, n, 0x1000000;\n@p bra LAB_WAIT;\ntrap;\nLAB_DONE:\n}\n"
               :: "r"(bar), "r"(parity) : "memory");
}
__device__ __forceinline__ void tma_load(uint32_t dst, const CUtensorMap* tm, int c0, int c1, uint32_t bar) {
  asm volatile("cp.async.bulk.tensor.2d.shared::cluster.global.mbarrier::complete_tx::bytes [%0], [%1, {%3, %4}], [%2];"
               :: "r"(dst), "l"(tm), "r"(bar), "r"(c0), "r"(c1) : "memory");
}
__device__ __forceinline__ void tma_load_mc(uint32_t dst, const CUtensorMap* tm, int c0, int c1, uint32_t bar) {
  asm volatile("cp.async.bulk.tensor.2d.shared::cluster.global.mbarrier::complete_tx::bytes.multicast::cluster [%0], [%1, {%3, %4}], [%2], %5;"
               :: "r"(dst), "l"(tm), "r"(bar), "r"(c0), "r"(c1), "h"((uint16_t)3) : "memory");
}
__device__ __forceinline__ unsigned lds_acquire(uint32_t a) {
  unsigned v; asm volatile("ld.acquire.cta.shared::cta.u32 %0, [%1];" : "=r"(v) : "r"(a) : "memory"); return v;
}
__device__ __forceinline__ void sts_release(uint32_t a, unsigned v) {
  asm volatile("st.release.cta.shared::cta.u32 [%0], %1;" :: "r"(a), "r"(v) : "memory");
}
__device__ __forceinline__ void bulk_load(uint32_t dst, const void* src, uint32_t bytes, uint32_t bar) {
  asm volatile("cp.async.bulk.shared::cluster.global.mbarrier::complete_tx::bytes [%0], [%1], %2, [%3];" :: "r"(dst), "l"(src), "r"(bytes), "r"(bar) : "memory");
}
__device__ __forceinline__ void tma_load_mc5(uint32_t dst, const CUtensorMap* tm, int c0, int c4, uint32_t bar) {
  asm volatile("cp.async.bulk.tensor.5d.shared::cluster.global.mbarrier::complete_tx::bytes.multicast::cluster [%0], [%1, {%3, %6, %6, %6, %4}], [%2], %5;"
               :: "r"(dst), "l"(tm), "r"(bar), "r"(c0), "r"(c4), "h"((uint16_t)3), "r"(0) : "memory");
}
__device__ __forceinline__ void wg_fence() { asm volatile("wgmma.fence.sync.aligned;" ::: "memory"); }
__device__ __forceinline__ void wg_commit() { asm volatile("wgmma.commit_group.sync.aligned;" ::: "memory"); }
template <int N> __device__ __forceinline__ void wg_wait() { asm volatile("wgmma.wait_group.sync.aligned %0;" :: "n"(N) : "memory"); }
template <int N> __device__ __forceinline__ void fence_regs(float (&a)[N]) {
#pragma unroll
  for (int i = 0; i < N; i++) asm volatile("" : "+f"(a[i]) :: "memory");
}
__device__ __forceinline__ uint32_t mkdesc(uint32_t addr, uint32_t lbo) { return ((addr & 0x3FFFF) >> 4) | ((lbo >> 4) << 16); }
__device__ __forceinline__ uint32_t pack_bf16(float lo, float hi) {
  uint32_t r; asm("cvt.rn.bf16x2.f32 %0, %1, %2;" : "=r"(r) : "f"(hi), "f"(lo)); return r;
}
__device__ __forceinline__ float rbf(float v) { return __bfloat162float(__float2bfloat16_rn(v)); }
__device__ __forceinline__ float bf_lo(uint32_t u) { return __uint_as_float(u << 16); }
__device__ __forceinline__ float bf_hi(uint32_t u) { return __uint_as_float(u & 0xffff0000u); }
__device__ __forceinline__ float ex2(float v) { float r; asm("ex2.approx.ftz.f32 %0, %1;" : "=f"(r) : "f"(v)); return r; }
__device__ __forceinline__ float rcp(float v) { float r; asm("rcp.approx.ftz.f32 %0, %1;" : "=f"(r) : "f"(v)); return r; }
__device__ __forceinline__ float silu_f(float v) { return v * rcp(1.0f + ex2(-1.4426950408889634f * v)); }
__device__ __forceinline__ uint32_t mul_bf16x2(uint32_t a, uint32_t b) {
  uint32_t r; asm("mul.rn.bf16x2 %0, %1, %2;" : "=r"(r) : "r"(a), "r"(b)); return r;
}
__device__ __forceinline__ uint32_t add_bf16x2(uint32_t a, uint32_t b) {
  uint32_t r; asm("add.rn.bf16x2 %0, %1, %2;" : "=r"(r) : "r"(a), "r"(b)); return r;
}
__device__ __forceinline__ unsigned ld_acquire(const unsigned* p) {
  unsigned v; asm volatile("ld.acquire.gpu.global.u32 %0, [%1];" : "=r"(v) : "l"(p) : "memory"); return v;
}
__device__ __forceinline__ void red_relaxed(unsigned* p, unsigned v) {
  asm volatile("red.relaxed.gpu.global.add.u32 [%0], %1;" :: "l"(p), "r"(v) : "memory");
}
__device__ __forceinline__ void st_relaxed(unsigned* p, unsigned v) {
  asm volatile("st.relaxed.gpu.global.u32 [%0], %1;" :: "l"(p), "r"(v) : "memory");
}
__device__ __forceinline__ bool elect() {
  uint32_t p;
  asm volatile("{\n.reg .pred p;\nelect.sync _|p, 0xffffffff;\nselp.u32 %0, 1, 0, p;\n}\n" : "=r"(p));
  return p != 0;
}
__device__ __forceinline__ void bar_sync(int id, int n) { asm volatile("bar.sync %0, %1;" :: "r"(id), "r"(n) : "memory"); }
__device__ __forceinline__ void bar_arrive(int id, int n) { asm volatile("bar.arrive %0, %1;" :: "r"(id), "r"(n) : "memory"); }

__device__ __forceinline__ void wgmma_ss_n64_k(float (&d)[32], uint32_t da, uint32_t db, int scale_d) {
  asm volatile("{\n.reg .pred p;\n.reg .b64 da, db;\nsetp.ne.b32 p, %34, 0;\n"
    "mov.b64 da, {%32, 0x40000040};\nmov.b64 db, {%33, 0x40000040};\n"
    "wgmma.mma_async.sync.aligned.m64n64k16.f32.bf16.bf16 {"
    "%0, %1, %2, %3, %4, %5, %6, %7, %8, %9, %10, %11, %12, %13, %14, %15,"
    "%16, %17, %18, %19, %20, %21, %22, %23, %24, %25, %26, %27, %28, %29, %30, %31"
    "}, da, db, p, 1, 1, 0, 0;\n}\n"
    : "+f"(d[0]), "+f"(d[1]), "+f"(d[2]), "+f"(d[3]), "+f"(d[4]), "+f"(d[5]), "+f"(d[6]), "+f"(d[7]),
      "+f"(d[8]), "+f"(d[9]), "+f"(d[10]), "+f"(d[11]), "+f"(d[12]), "+f"(d[13]), "+f"(d[14]), "+f"(d[15]),
      "+f"(d[16]), "+f"(d[17]), "+f"(d[18]), "+f"(d[19]), "+f"(d[20]), "+f"(d[21]), "+f"(d[22]), "+f"(d[23]),
      "+f"(d[24]), "+f"(d[25]), "+f"(d[26]), "+f"(d[27]), "+f"(d[28]), "+f"(d[29]), "+f"(d[30]), "+f"(d[31])
    : "r"(da), "r"(db), "r"(scale_d));
}
__device__ __forceinline__ void wgmma_ss_n256_t(float (&d)[128], uint32_t da, uint32_t db, int scale_d) {
  asm volatile("{\n.reg .pred p;\n.reg .b64 da, db;\nsetp.ne.b32 p, %130, 0;\n"
    "mov.b64 da, {%128, 0x40000040};\nmov.b64 db, {%129, 0x40000040};\n"
    "wgmma.mma_async.sync.aligned.m64n256k16.f32.bf16.bf16 {"
    "%0, %1, %2, %3, %4, %5, %6, %7, %8, %9, %10, %11, %12, %13, %14, %15,"
    "%16, %17, %18, %19, %20, %21, %22, %23, %24, %25, %26, %27, %28, %29, %30, %31,"
    "%32, %33, %34, %35, %36, %37, %38, %39, %40, %41, %42, %43, %44, %45, %46, %47,"
    "%48, %49, %50, %51, %52, %53, %54, %55, %56, %57, %58, %59, %60, %61, %62, %63,"
    "%64, %65, %66, %67, %68, %69, %70, %71, %72, %73, %74, %75, %76, %77, %78, %79,"
    "%80, %81, %82, %83, %84, %85, %86, %87, %88, %89, %90, %91, %92, %93, %94, %95,"
    "%96, %97, %98, %99, %100, %101, %102, %103, %104, %105, %106, %107, %108, %109, %110, %111,"
    "%112, %113, %114, %115, %116, %117, %118, %119, %120, %121, %122, %123, %124, %125, %126, %127"
    "}, da, db, p, 1, 1, 0, 1;\n}\n"
    : "+f"(d[0]), "+f"(d[1]), "+f"(d[2]), "+f"(d[3]), "+f"(d[4]), "+f"(d[5]), "+f"(d[6]), "+f"(d[7]),
      "+f"(d[8]), "+f"(d[9]), "+f"(d[10]), "+f"(d[11]), "+f"(d[12]), "+f"(d[13]), "+f"(d[14]), "+f"(d[15]),
      "+f"(d[16]), "+f"(d[17]), "+f"(d[18]), "+f"(d[19]), "+f"(d[20]), "+f"(d[21]), "+f"(d[22]), "+f"(d[23]),
      "+f"(d[24]), "+f"(d[25]), "+f"(d[26]), "+f"(d[27]), "+f"(d[28]), "+f"(d[29]), "+f"(d[30]), "+f"(d[31]),
      "+f"(d[32]), "+f"(d[33]), "+f"(d[34]), "+f"(d[35]), "+f"(d[36]), "+f"(d[37]), "+f"(d[38]), "+f"(d[39]),
      "+f"(d[40]), "+f"(d[41]), "+f"(d[42]), "+f"(d[43]), "+f"(d[44]), "+f"(d[45]), "+f"(d[46]), "+f"(d[47]),
      "+f"(d[48]), "+f"(d[49]), "+f"(d[50]), "+f"(d[51]), "+f"(d[52]), "+f"(d[53]), "+f"(d[54]), "+f"(d[55]),
      "+f"(d[56]), "+f"(d[57]), "+f"(d[58]), "+f"(d[59]), "+f"(d[60]), "+f"(d[61]), "+f"(d[62]), "+f"(d[63]),
      "+f"(d[64]), "+f"(d[65]), "+f"(d[66]), "+f"(d[67]), "+f"(d[68]), "+f"(d[69]), "+f"(d[70]), "+f"(d[71]),
      "+f"(d[72]), "+f"(d[73]), "+f"(d[74]), "+f"(d[75]), "+f"(d[76]), "+f"(d[77]), "+f"(d[78]), "+f"(d[79]),
      "+f"(d[80]), "+f"(d[81]), "+f"(d[82]), "+f"(d[83]), "+f"(d[84]), "+f"(d[85]), "+f"(d[86]), "+f"(d[87]),
      "+f"(d[88]), "+f"(d[89]), "+f"(d[90]), "+f"(d[91]), "+f"(d[92]), "+f"(d[93]), "+f"(d[94]), "+f"(d[95]),
      "+f"(d[96]), "+f"(d[97]), "+f"(d[98]), "+f"(d[99]), "+f"(d[100]), "+f"(d[101]), "+f"(d[102]), "+f"(d[103]),
      "+f"(d[104]), "+f"(d[105]), "+f"(d[106]), "+f"(d[107]), "+f"(d[108]), "+f"(d[109]), "+f"(d[110]), "+f"(d[111]),
      "+f"(d[112]), "+f"(d[113]), "+f"(d[114]), "+f"(d[115]), "+f"(d[116]), "+f"(d[117]), "+f"(d[118]), "+f"(d[119]),
      "+f"(d[120]), "+f"(d[121]), "+f"(d[122]), "+f"(d[123]), "+f"(d[124]), "+f"(d[125]), "+f"(d[126]), "+f"(d[127])
    : "r"(da), "r"(db), "r"(scale_d));
}
__device__ __forceinline__ void wgmma_rs_n256_t(float (&d)[128], uint32_t a0, uint32_t a1, uint32_t a2, uint32_t a3, uint32_t db, int scale_d) {
  asm volatile("{\n.reg .pred p;\n.reg .b64 db;\nsetp.ne.b32 p, %133, 0;\n"
    "mov.b64 db, {%132, 0x40000040};\n"
    "wgmma.mma_async.sync.aligned.m64n256k16.f32.bf16.bf16 {"
    "%0, %1, %2, %3, %4, %5, %6, %7, %8, %9, %10, %11, %12, %13, %14, %15,"
    "%16, %17, %18, %19, %20, %21, %22, %23, %24, %25, %26, %27, %28, %29, %30, %31,"
    "%32, %33, %34, %35, %36, %37, %38, %39, %40, %41, %42, %43, %44, %45, %46, %47,"
    "%48, %49, %50, %51, %52, %53, %54, %55, %56, %57, %58, %59, %60, %61, %62, %63,"
    "%64, %65, %66, %67, %68, %69, %70, %71, %72, %73, %74, %75, %76, %77, %78, %79,"
    "%80, %81, %82, %83, %84, %85, %86, %87, %88, %89, %90, %91, %92, %93, %94, %95,"
    "%96, %97, %98, %99, %100, %101, %102, %103, %104, %105, %106, %107, %108, %109, %110, %111,"
    "%112, %113, %114, %115, %116, %117, %118, %119, %120, %121, %122, %123, %124, %125, %126, %127"
    "}, {%128, %129, %130, %131}, db, p, 1, 1, 1;\n}\n"
    : "+f"(d[0]), "+f"(d[1]), "+f"(d[2]), "+f"(d[3]), "+f"(d[4]), "+f"(d[5]), "+f"(d[6]), "+f"(d[7]),
      "+f"(d[8]), "+f"(d[9]), "+f"(d[10]), "+f"(d[11]), "+f"(d[12]), "+f"(d[13]), "+f"(d[14]), "+f"(d[15]),
      "+f"(d[16]), "+f"(d[17]), "+f"(d[18]), "+f"(d[19]), "+f"(d[20]), "+f"(d[21]), "+f"(d[22]), "+f"(d[23]),
      "+f"(d[24]), "+f"(d[25]), "+f"(d[26]), "+f"(d[27]), "+f"(d[28]), "+f"(d[29]), "+f"(d[30]), "+f"(d[31]),
      "+f"(d[32]), "+f"(d[33]), "+f"(d[34]), "+f"(d[35]), "+f"(d[36]), "+f"(d[37]), "+f"(d[38]), "+f"(d[39]),
      "+f"(d[40]), "+f"(d[41]), "+f"(d[42]), "+f"(d[43]), "+f"(d[44]), "+f"(d[45]), "+f"(d[46]), "+f"(d[47]),
      "+f"(d[48]), "+f"(d[49]), "+f"(d[50]), "+f"(d[51]), "+f"(d[52]), "+f"(d[53]), "+f"(d[54]), "+f"(d[55]),
      "+f"(d[56]), "+f"(d[57]), "+f"(d[58]), "+f"(d[59]), "+f"(d[60]), "+f"(d[61]), "+f"(d[62]), "+f"(d[63]),
      "+f"(d[64]), "+f"(d[65]), "+f"(d[66]), "+f"(d[67]), "+f"(d[68]), "+f"(d[69]), "+f"(d[70]), "+f"(d[71]),
      "+f"(d[72]), "+f"(d[73]), "+f"(d[74]), "+f"(d[75]), "+f"(d[76]), "+f"(d[77]), "+f"(d[78]), "+f"(d[79]),
      "+f"(d[80]), "+f"(d[81]), "+f"(d[82]), "+f"(d[83]), "+f"(d[84]), "+f"(d[85]), "+f"(d[86]), "+f"(d[87]),
      "+f"(d[88]), "+f"(d[89]), "+f"(d[90]), "+f"(d[91]), "+f"(d[92]), "+f"(d[93]), "+f"(d[94]), "+f"(d[95]),
      "+f"(d[96]), "+f"(d[97]), "+f"(d[98]), "+f"(d[99]), "+f"(d[100]), "+f"(d[101]), "+f"(d[102]), "+f"(d[103]),
      "+f"(d[104]), "+f"(d[105]), "+f"(d[106]), "+f"(d[107]), "+f"(d[108]), "+f"(d[109]), "+f"(d[110]), "+f"(d[111]),
      "+f"(d[112]), "+f"(d[113]), "+f"(d[114]), "+f"(d[115]), "+f"(d[116]), "+f"(d[117]), "+f"(d[118]), "+f"(d[119]),
      "+f"(d[120]), "+f"(d[121]), "+f"(d[122]), "+f"(d[123]), "+f"(d[124]), "+f"(d[125]), "+f"(d[126]), "+f"(d[127])
    : "r"(a0), "r"(a1), "r"(a2), "r"(a3), "r"(db), "r"(scale_d));
}
__device__ __forceinline__ void wgmma_rs_n128_t(float (&d)[64], uint32_t a0, uint32_t a1, uint32_t a2, uint32_t a3, uint32_t db, int scale_d) {
  asm volatile("{\n.reg .pred p;\n.reg .b64 db;\nsetp.ne.b32 p, %69, 0;\n"
    "mov.b64 db, {%68, 0x40000040};\n"
    "wgmma.mma_async.sync.aligned.m64n128k16.f32.bf16.bf16 {"
    "%0, %1, %2, %3, %4, %5, %6, %7, %8, %9, %10, %11, %12, %13, %14, %15,"
    "%16, %17, %18, %19, %20, %21, %22, %23, %24, %25, %26, %27, %28, %29, %30, %31,"
    "%32, %33, %34, %35, %36, %37, %38, %39, %40, %41, %42, %43, %44, %45, %46, %47,"
    "%48, %49, %50, %51, %52, %53, %54, %55, %56, %57, %58, %59, %60, %61, %62, %63"
    "}, {%64, %65, %66, %67}, db, p, 1, 1, 1;\n}\n"
    : "+f"(d[0]), "+f"(d[1]), "+f"(d[2]), "+f"(d[3]), "+f"(d[4]), "+f"(d[5]), "+f"(d[6]), "+f"(d[7]),
      "+f"(d[8]), "+f"(d[9]), "+f"(d[10]), "+f"(d[11]), "+f"(d[12]), "+f"(d[13]), "+f"(d[14]), "+f"(d[15]),
      "+f"(d[16]), "+f"(d[17]), "+f"(d[18]), "+f"(d[19]), "+f"(d[20]), "+f"(d[21]), "+f"(d[22]), "+f"(d[23]),
      "+f"(d[24]), "+f"(d[25]), "+f"(d[26]), "+f"(d[27]), "+f"(d[28]), "+f"(d[29]), "+f"(d[30]), "+f"(d[31]),
      "+f"(d[32]), "+f"(d[33]), "+f"(d[34]), "+f"(d[35]), "+f"(d[36]), "+f"(d[37]), "+f"(d[38]), "+f"(d[39]),
      "+f"(d[40]), "+f"(d[41]), "+f"(d[42]), "+f"(d[43]), "+f"(d[44]), "+f"(d[45]), "+f"(d[46]), "+f"(d[47]),
      "+f"(d[48]), "+f"(d[49]), "+f"(d[50]), "+f"(d[51]), "+f"(d[52]), "+f"(d[53]), "+f"(d[54]), "+f"(d[55]),
      "+f"(d[56]), "+f"(d[57]), "+f"(d[58]), "+f"(d[59]), "+f"(d[60]), "+f"(d[61]), "+f"(d[62]), "+f"(d[63])
    : "r"(a0), "r"(a1), "r"(a2), "r"(a3), "r"(db), "r"(scale_d));
}
__device__ __forceinline__ void wgmma_rs_n64_t(float (&d)[32], uint32_t a0, uint32_t a1, uint32_t a2, uint32_t a3, uint32_t db, int scale_d) {
  asm volatile("{\n.reg .pred p;\n.reg .b64 db;\nsetp.ne.b32 p, %37, 0;\n"
    "mov.b64 db, {%36, 0x40000040};\n"
    "wgmma.mma_async.sync.aligned.m64n64k16.f32.bf16.bf16 {"
    "%0, %1, %2, %3, %4, %5, %6, %7, %8, %9, %10, %11, %12, %13, %14, %15,"
    "%16, %17, %18, %19, %20, %21, %22, %23, %24, %25, %26, %27, %28, %29, %30, %31"
    "}, {%32, %33, %34, %35}, db, p, 1, 1, 1;\n}\n"
    : "+f"(d[0]), "+f"(d[1]), "+f"(d[2]), "+f"(d[3]), "+f"(d[4]), "+f"(d[5]), "+f"(d[6]), "+f"(d[7]),
      "+f"(d[8]), "+f"(d[9]), "+f"(d[10]), "+f"(d[11]), "+f"(d[12]), "+f"(d[13]), "+f"(d[14]), "+f"(d[15]),
      "+f"(d[16]), "+f"(d[17]), "+f"(d[18]), "+f"(d[19]), "+f"(d[20]), "+f"(d[21]), "+f"(d[22]), "+f"(d[23]),
      "+f"(d[24]), "+f"(d[25]), "+f"(d[26]), "+f"(d[27]), "+f"(d[28]), "+f"(d[29]), "+f"(d[30]), "+f"(d[31])
    : "r"(a0), "r"(a1), "r"(a2), "r"(a3), "r"(db), "r"(scale_d));
}
__device__ __forceinline__ void wgmma_ss_n128_t(float (&d)[64], uint32_t da, uint32_t db, int scale_d) {
  asm volatile("{\n.reg .pred p;\n.reg .b64 da, db;\nsetp.ne.b32 p, %66, 0;\n"
    "mov.b64 da, {%64, 0x40000040};\nmov.b64 db, {%65, 0x40000040};\n"
    "wgmma.mma_async.sync.aligned.m64n128k16.f32.bf16.bf16 {"
    "%0, %1, %2, %3, %4, %5, %6, %7, %8, %9, %10, %11, %12, %13, %14, %15,"
    "%16, %17, %18, %19, %20, %21, %22, %23, %24, %25, %26, %27, %28, %29, %30, %31,"
    "%32, %33, %34, %35, %36, %37, %38, %39, %40, %41, %42, %43, %44, %45, %46, %47,"
    "%48, %49, %50, %51, %52, %53, %54, %55, %56, %57, %58, %59, %60, %61, %62, %63"
    "}, da, db, p, 1, 1, 0, 1;\n}\n"
    : "+f"(d[0]), "+f"(d[1]), "+f"(d[2]), "+f"(d[3]), "+f"(d[4]), "+f"(d[5]), "+f"(d[6]), "+f"(d[7]),
      "+f"(d[8]), "+f"(d[9]), "+f"(d[10]), "+f"(d[11]), "+f"(d[12]), "+f"(d[13]), "+f"(d[14]), "+f"(d[15]),
      "+f"(d[16]), "+f"(d[17]), "+f"(d[18]), "+f"(d[19]), "+f"(d[20]), "+f"(d[21]), "+f"(d[22]), "+f"(d[23]),
      "+f"(d[24]), "+f"(d[25]), "+f"(d[26]), "+f"(d[27]), "+f"(d[28]), "+f"(d[29]), "+f"(d[30]), "+f"(d[31]),
      "+f"(d[32]), "+f"(d[33]), "+f"(d[34]), "+f"(d[35]), "+f"(d[36]), "+f"(d[37]), "+f"(d[38]), "+f"(d[39]),
      "+f"(d[40]), "+f"(d[41]), "+f"(d[42]), "+f"(d[43]), "+f"(d[44]), "+f"(d[45]), "+f"(d[46]), "+f"(d[47]),
      "+f"(d[48]), "+f"(d[49]), "+f"(d[50]), "+f"(d[51]), "+f"(d[52]), "+f"(d[53]), "+f"(d[54]), "+f"(d[55]),
      "+f"(d[56]), "+f"(d[57]), "+f"(d[58]), "+f"(d[59]), "+f"(d[60]), "+f"(d[61]), "+f"(d[62]), "+f"(d[63])
    : "r"(da), "r"(db), "r"(scale_d));
}
__device__ __forceinline__ void wgmma_ss_n64_t(float (&d)[32], uint32_t da, uint32_t db, int scale_d) {
  asm volatile("{\n.reg .pred p;\n.reg .b64 da, db;\nsetp.ne.b32 p, %34, 0;\n"
    "mov.b64 da, {%32, 0x40000040};\nmov.b64 db, {%33, 0x40000040};\n"
    "wgmma.mma_async.sync.aligned.m64n64k16.f32.bf16.bf16 {"
    "%0, %1, %2, %3, %4, %5, %6, %7, %8, %9, %10, %11, %12, %13, %14, %15,"
    "%16, %17, %18, %19, %20, %21, %22, %23, %24, %25, %26, %27, %28, %29, %30, %31"
    "}, da, db, p, 1, 1, 0, 1;\n}\n"
    : "+f"(d[0]), "+f"(d[1]), "+f"(d[2]), "+f"(d[3]), "+f"(d[4]), "+f"(d[5]), "+f"(d[6]), "+f"(d[7]),
      "+f"(d[8]), "+f"(d[9]), "+f"(d[10]), "+f"(d[11]), "+f"(d[12]), "+f"(d[13]), "+f"(d[14]), "+f"(d[15]),
      "+f"(d[16]), "+f"(d[17]), "+f"(d[18]), "+f"(d[19]), "+f"(d[20]), "+f"(d[21]), "+f"(d[22]), "+f"(d[23]),
      "+f"(d[24]), "+f"(d[25]), "+f"(d[26]), "+f"(d[27]), "+f"(d[28]), "+f"(d[29]), "+f"(d[30]), "+f"(d[31])
    : "r"(da), "r"(db), "r"(scale_d));
}


template <int V> struct IC { static constexpr int value = V; };

__device__ __forceinline__ int park_slot(int type, int h) { return (type == T_ATT ? 0 : 8) + (h >> 1); }
__device__ __forceinline__ int blk64_of(int type, int rb, int rank, int w) {
  if (type == T_ATT) return rb * 4 + (rank == 0 ? (w == 0 ? 0 : 3) : (w == 0 ? 1 : 2));
  return rb * 4 + rank * 2 + w;
}

__global__ void __cluster_dims__(2, 1, 1) __launch_bounds__(384, 1)
fused_kernel(const __grid_constant__ Params P) {
  extern __shared__ uint8_t smem_raw[];
  const uint32_t sbase = (smem_u32(smem_raw) + 1023) & ~1023u;
  const uint32_t sA = sbase, sB = sbase + NA * A_UNIT, sBar = sbase + SMEM_DATA;
  const uint32_t fullB = sBar, emptyB = sBar + 8 * NB, emptyA = sBar + 16 * NB;
  const uint32_t ackBar = emptyA + 8 * NA, epBar = ackBar + 16, sEpoch = epBar + 8, sDeps = sEpoch + 4, cmbBar = sBar + 384;
  const int tid = threadIdx.x, warp = __shfl_sync(0xffffffffu, tid >> 5, 0), lane = tid & 31;
  const uint32_t rank = blockIdx.x & 1;
  const int cl = blockIdx.x >> 1;
  const uint16_t* sched = P.sched[cl];

  uint2 lnu[2][7];
  const int lnrow = blockIdx.x * 16 + (warp - 8) * 4 + (lane >> 4);
  if (warp >= 8 && lnrow < SEQ) {
    const uint2* xr = reinterpret_cast<const uint2*>(P.x + lnrow * DM) + (lane & 15);
#pragma unroll
    for (int i = 0; i < 14; i++)
      asm volatile("ld.global.nc.v2.u32 {%0, %1}, [%2];" : "=r"(lnu[i / 7][i % 7].x), "=r"(lnu[i / 7][i % 7].y) : "l"(xr + (i / 7) * (DM / 2) + 16 * (i % 7)));
  }
  if (tid == 32) {
    asm volatile("prefetch.tensormap [%0];" :: "l"(&P.tm_ckv) : "memory");
    asm volatile("prefetch.tensormap [%0];" :: "l"(&P.tm_wuk) : "memory");
    asm volatile("prefetch.tensormap [%0];" :: "l"(&P.tm_wuv) : "memory");
  }
  if (tid == 0) {
#pragma unroll
    for (int i = 0; i < 17; i++) mbar_init(sBar + 8 * i, i < NB ? 1 : i < 2 * NB ? 4 : i < 2 * NB + NA ? 2 : 1);
#pragma unroll
    for (int i = 0; i < NCMB; i++) mbar_init(cmbBar + 8 * i, 1);
    asm volatile("st.shared.u32 [%0], %1;" :: "r"(sDeps), "r"(0) : "memory");
    asm volatile("fence.mbarrier_init.release.cluster;" ::: "memory");
  }
  __syncthreads();
  asm volatile("barrier.cluster.arrive.relaxed.aligned;\nbarrier.cluster.wait.aligned;" ::: "memory");
  const int npre = (sched[0] >> 14) == T_KV ? NA : 0;
  if (tid == 0) {
    const int code = sched[0];
    const CUtensorMap* tm = (code & 128) ? &P.tm_wuv : &P.tm_wuk;
    const int c0 = ((code >> 3) & 15) * 256 + rank * 128, r0 = (code & 7) * 256 + rank * 128;
#pragma unroll 1
    for (int i = 0; i < npre; i++) {
      const uint32_t fb = fullB + 8 * i, d = sB + i * B_SLOT + rank * 16384;
      mbar_expect_tx(fb, B_SLOT + A_UNIT);
      tma_load_mc(d, tm, c0, i * 64, fb);
      tma_load_mc(d + 8192, tm, c0 + 64, i * 64, fb);
      tma_load(sA + i * A_UNIT, &P.tm_ckv, i * 64, r0, fb);
      tma_load(sA + i * A_UNIT + 8192, &P.tm_ckv, i * 64, r0 + 64, fb);
    }
  }
  auto get_epoch = [&]() -> unsigned {
    mbar_wait(epBar, 0);
    unsigned e; asm volatile("ld.shared.u32 %0, [%1];" : "=r"(e) : "r"(sEpoch) : "memory");
    return e;
  };

  if (warp >= 8) {
    const int hl = lane & 15;
    for (int row0 = lnrow; row0 - (lane >> 4) < SEQ; row0 += gridDim.x * 16) {
      if (row0 != lnrow) {
#pragma unroll
        for (int i = 0; i < 14; i++) lnu[i / 7][i % 7] = __ldg(reinterpret_cast<const uint2*>(P.x + (row0 + (i / 7) * 2) * DM) + hl + 16 * (i % 7));
      }
      float s[2], q[2];
#pragma unroll
      for (int r = 0; r < 2; r++) {
        s[r] = 0.f;
#pragma unroll
        for (int i = 0; i < 7; i++) s[r] += (bf_lo(lnu[r][i].x) + bf_hi(lnu[r][i].x)) + (bf_lo(lnu[r][i].y) + bf_hi(lnu[r][i].y));
      }
#pragma unroll
      for (int o = 8; o; o >>= 1) { s[0] += __shfl_xor_sync(0xffffffffu, s[0], o); s[1] += __shfl_xor_sync(0xffffffffu, s[1], o); }
#pragma unroll
      for (int r = 0; r < 2; r++) {
        const float mean = s[r] * (1.0f / DM);
        q[r] = 0.f;
#pragma unroll
        for (int i = 0; i < 7; i++) {
          const float a = bf_lo(lnu[r][i].x) - mean, b = bf_hi(lnu[r][i].x) - mean, c = bf_lo(lnu[r][i].y) - mean, d = bf_hi(lnu[r][i].y) - mean;
          q[r] += (a * a + b * b) + (c * c + d * d);
        }
      }
#pragma unroll
      for (int o = 8; o; o >>= 1) { q[0] += __shfl_xor_sync(0xffffffffu, q[0], o); q[1] += __shfl_xor_sync(0xffffffffu, q[1], o); }
#pragma unroll
      for (int r = 0; r < 2; r++) {
        const float mb = rbf(s[r] * (1.0f / DM));
        float sd; asm("sqrt.approx.f32 %0, %1;" : "=f"(sd) : "f"(rbf(rbf(q[r] * (1.0f / DM)) + 1e-5f)));
        const float rs = rcp(rbf(sd));
        uint2* xo = reinterpret_cast<uint2*>(g_xn + (row0 + r * 2) * DM) + hl;
#pragma unroll
        for (int i = 0; i < 7; i++) {
          const uint32_t d0 = pack_bf16(bf_lo(lnu[r][i].x) - mb, bf_hi(lnu[r][i].x) - mb), d1 = pack_bf16(bf_lo(lnu[r][i].y) - mb, bf_hi(lnu[r][i].y) - mb);
          xo[16 * i] = make_uint2(pack_bf16(bf_lo(d0) * rs, bf_hi(d0) * rs), pack_bf16(bf_lo(d1) * rs, bf_hi(d1) * rs));
        }
      }
    }
    bar_arrive(7, 160);
  }

  if (warp < 4) {
    asm volatile("setmaxnreg.dec.sync.aligned.u32 40;");
    if (warp == 0) {
      int sb = npre, pb = 1, sa = 0, pa = npre ? 0 : 1;
      unsigned ndep = 0;
      bool first_x = true;
      auto depend = [&]() {
        ndep++;
        for (unsigned n = 0; lds_acquire(sDeps) < ndep && n < SPIN_LIMIT; n++) __nanosleep(40);
        asm volatile("fence.proxy.async.global;" ::: "memory");
      };
      auto loadB = [&](const CUtensorMap* tm, int c0, int r0, int c1, int r1, uint32_t extra) {
        mbar_wait(emptyB + 8 * sb, pb);
        if (elect()) {
          const uint32_t fb = fullB + 8 * sb, d = sB + sb * B_SLOT + rank * 16384;
          mbar_expect_tx(fb, B_SLOT + extra);
          tma_load_mc(d, tm, c0, r0, fb);
          tma_load_mc(d + 8192, tm, c1, r1, fb);
        }
      };
      auto loadA = [&](const CUtensorMap* ta, int c, int row0, int row1) {
        mbar_wait(emptyA + 8 * sa, pa);
        if (elect()) {
          tma_load(sA + sa * A_UNIT, ta, c, row0, fullB + 8 * sb);
          tma_load(sA + sa * A_UNIT + 8192, ta, c, row1, fullB + 8 * sb);
        }
        if (++sa == NA) { sa = 0; pa ^= 1; }
      };
      auto advB = [&]() { if (++sb == NB) { sb = 0; pb ^= 1; } };
      for (int it = 0; it < MAX_ITEMS; it++) {
        const int code = sched[it], type = code >> 14, mode = (code >> 12) & 3;
        if (type == T_END) break;
        const int rb = code & 7, h = (code >> 3) & 15;
        const int row0 = blk64_of(type, rb, rank, 0) * 64, row1 = blk64_of(type, rb, rank, 1) * 64;
        if (type != T_KV && first_x) { depend(); first_x = false; }
        {
          const CUtensorMap* tm = type == T_KV ? ((code & 128) ? &P.tm_wuv : &P.tm_wuk) : (type == T_ATT ? &P.tm_wq : (rank ? &P.tm_wu : &P.tm_wg));
          const CUtensorMap* ta = type == T_KV ? &P.tm_ckv : &P.tm_xn;
          const int ng = type == T_KV ? 16 : (type == T_ATT ? 7 : 14);
          int c0 = h * 256 + (type == T_FFN ? 0 : rank * 128), k = it ? 0 : npre * 64;
#pragma unroll 1
          for (int i = it ? 0 : npre; i < ng; i++) {
            loadB(tm, c0, k, c0 + 64, k, A_UNIT);
            loadA(ta, k, row0, row1);
            advB();
            k += 64;
            if (type == T_FFN && i == 6) { k = 0; c0 += 128; }
          }
        }
        if (type == T_ATT) {
          const int nkv = 8 * rb + 8, ck = h * 256 + rank * 128;
#pragma unroll 1
          for (int q = 0; q < nkv; q++) {
            const bool isv = q == nkv - 1 || (q > 0 && (q & 1) == 0);
            const int t = isv ? ((q + 1) >> 1) - 1 : (q + 1) >> 1, c = ck + (isv ? NH * HD : 0);
            if (!isv && (t & 3) == 0) depend();
            loadB(&P.tm_kv, c, t * 64, c + 64, t * 64, 0);
            advB();
          }
        }
        if (type == T_KV || mode == M_PARK) continue;
        const bool merge = mode == M_MERGE;
#pragma unroll 1
        for (int q = 0; q < (merge ? 14 : 7); q++) {
          const int c = merge ? q >> 2 : q >> 1, other = !merge ? 0 : (c < 3 ? (q >> 1) & 1 : (q & 1) ^ 1);
          const int r0 = (h ^ other) * 256 + (c < 3 ? (q & 1) * 128 + rank * 64 : rank * 128);
          const bool parked = merge && q == 2;
          if (parked) depend();
          const CUtensorMap* tm = &P.tm_proj[type == T_ATT ? other ^ 1 : 2 + other];
          mbar_wait(emptyB + 8 * sb, pb);
          if (elect()) {
            const uint32_t fb = fullB + 8 * sb, d = sB + sb * B_SLOT + rank * 16384;
            mbar_expect_tx(fb, B_SLOT + (parked ? NA * A_UNIT : 0));
            tma_load_mc5(d, tm, c * 128, r0 >> 5, fb);
            tma_load_mc5(d + 8192, tm, c < 3 ? c * 128 + 64 : 384, (r0 >> 5) + (c < 3 ? 0 : 2), fb);
          }
          if (parked) {
#pragma unroll 1
            for (int u = 0; u < NA; u++) loadA(&P.tm_kv, 2 * NH * HD + park_slot(type, h) * 256 + u * 64, row0, row1);
          }
          advB();
        }
      }
      depend();
      const unsigned e = get_epoch();
      for (int slice = blockIdx.x; slice < 128; slice += gridDim.x) {
        const int sb0 = sb, sa0 = sa;
        unsigned done = 0x3fff0000u, ready = 0xc0000000u;
        int at = 0, have = 0;
#pragma unroll 1
        for (unsigned n = 0; at < NCMB && n < SPIN_LIMIT; n++) {
          if (ready) {
#pragma unroll 1
            for (; have < at + __popc(ready); have++) {
              if (have >= 6) { mbar_wait(emptyA + 8 * sa, pa); if (++sa == NA) { sa = 0; pa ^= 1; } }
              else if ((have & 1) == 0) { mbar_wait(emptyB + 8 * sb, pb); advB(); }
            }
            asm volatile("fence.proxy.async.global;" ::: "memory");
            if ((ready >> lane) & 1) {
              const int i = at + __popc(ready & ((1u << lane) - 1)), sl = sb0 + (i >> 1);
              const uint32_t d = i >= 6 ? sA + ((sa0 + i - 6) & (NA - 1)) * A_UNIT : sB + (sl >= NB ? sl - NB : sl) * B_SLOT + (i & 1) * (NV4 * 512);
              const void* src = lane == 31 ? (const void*)(P.x + slice * 16 * DM) : (const void*)&g_part[lane == 30 ? NPART - 1 : lane][slice * NV4 * 32];
              mbar_expect_tx(cmbBar + 8 * i, NV4 * 512);
              bulk_load(d, src, NV4 * 512, cmbBar + 8 * i);
            }
            at += __popc(ready);
            done |= ready;
            __syncwarp();
          }
          ready = __ballot_sync(0xffffffffu, ld_acquire(&g_pflag[slice >> 2][lane]) == e) & ~done;
        }
      }
    } else if (warp == 3) {
      const unsigned e = ld_relaxed(&g_epoch) + 1;
      if (lane == 0) {
        asm volatile("st.shared.u32 [%0], %1;" :: "r"(sEpoch), "r"(e) : "memory");
        mbar_arrive(epBar);
      }
      int gslice = blockIdx.x, gv = 0;
      unsigned ymask = 0;
      auto gate_step = [&]() {
        if (gslice >= 128) { __nanosleep(POLL_NS); return; }
        if (__popc(ymask) < 4) {
          ymask = __ballot_sync(0xffffffffu, ld_acquire(&g_pflag[gslice >> 2][lane]) == e) >> NH;
          if (__popc(ymask) < 4) { __nanosleep(POLL_NS); return; }
          if ((ymask >> lane) & 1)
            asm volatile("cp.async.bulk.prefetch.L2.global [%0], %1;" :: "l"(&g_part[NH + lane][gslice * NV4 * 32]), "r"(NV4 * 512) : "memory");
          __syncwarp();
        }
#pragma unroll 1
        for (int r = 0; r < 4; r++, gv++) {
          const int o = (gslice * NV4 + gv) * 32 + lane;
          uint4 v[4];
          unsigned m = ymask;
#pragma unroll
          for (int j = 0; j < 4; j++) { v[j] = __ldcg(&g_part[NH + __ffs(m) - 1][o]); m &= m - 1; }
          auto g2 = [](uint32_t a, uint32_t b, uint32_t c, uint32_t d) {
            const uint32_t yp = pack_bf16((bf_lo(a) + bf_lo(b)) + (bf_lo(c) + bf_lo(d)), (bf_hi(a) + bf_hi(b)) + (bf_hi(c) + bf_hi(d)));
            return pack_bf16(silu_f(bf_lo(yp)), silu_f(bf_hi(yp)));
          };
          g_part[NPART - 1][o] = make_uint4(g2(v[0].x, v[1].x, v[2].x, v[3].x), g2(v[0].y, v[1].y, v[2].y, v[3].y),
                                            g2(v[0].z, v[1].z, v[2].z, v[3].z), g2(v[0].w, v[1].w, v[2].w, v[3].w));
        }
        if (gv == NV4) { gv = 0; gslice += gridDim.x; ymask = 0; }
      };
      {
        unsigned ndep = 0;
        bool first_x = true;
        for (int it = 0; it <= MAX_ITEMS; it++) {
          const int code = it < MAX_ITEMS ? sched[it] : T_END << 14, type = code >> 14, mode = (code >> 12) & 3;
          if (type == T_KV) continue;
          const int rb = code & 7, h = (code >> 3) & 15;
          const int nk = type == T_ATT ? 2 * rb + 2 : 0;
#pragma unroll 1
          for (int q = -1; q < nk + 1; q++) {
            const unsigned* f;
            unsigned target = e * 4;
            if (q < 0) { if (!first_x) continue; first_x = false; f = &g_ln; target = e * gridDim.x; }
            else if (q < nk) f = &g_kvflag[(q & 1) * 128 + h * 8 + (q >> 1)];
            else { if (mode != M_MERGE && type != T_END) continue; f = &g_kvflag[256 + park_slot(type, h) * 8 + rb]; }
            for (unsigned n = 0; n < SPIN_LIMIT && (q >= 0 && type == T_END ? gslice < 128 : (int)(ld_acquire(f) - target) < 0); n++) gate_step();
            if (q >= 0 && q < nk && (q & 1) == 0) continue;
            if (q < 0 && type == T_END) continue;
            ++ndep;
            if (type == T_END) asm volatile("fence.proxy.async.global;" ::: "memory");
            __syncwarp();
            if (lane == 0) sts_release(sDeps, ndep);
          }
          if (type == T_END) break;
        }
        if (blockIdx.x == 0 && lane == 0) *(volatile unsigned*)&g_epoch = e;
      }
    } else {
      if (warp == 1) {
        bar_sync(7, 160);
        if (lane == 0) {
          mbar_wait_bg(epBar, 0);
          asm volatile("fence.proxy.async.global;\nfence.acq_rel.gpu;" ::: "memory");
          red_relaxed(&g_ln, 1);
        }
        __syncwarp();
      }
      {
        const int w = warp - 1;
        int cnt = 0;
        for (int it = 0; it < MAX_ITEMS; it++) {
          const int code = sched[it], type = code >> 14, mode = (code >> 12) & 3;
          if (type == T_END) break;
          const int rb = code & 7, h = (code >> 3) & 15;
          const int nload = type == T_KV ? 16 : (type == T_ATT ? 7 + 2 * (4 * rb + 4) : 14);
          const bool stores = type == T_KV || mode == M_PARK;
          if (type == T_ATT && blk64_of(T_ATT, rb, rank, w) + 1 < 4 * rb + 4) {
            bar_sync(5 + w, 160);
            if (lane == 0) {
              const int n = blk64_of(T_ATT, rb, rank, w) + 1;
              for (int c = cnt + 7 + 2 * n - 1; c < cnt + 7 + 2 * (4 * rb + 4); c++) {
                const int slot = c % NB;
                mbar_wait_bg(fullB + 8 * slot, (c / NB) & 1);
                if (c == cnt + 7 + 2 * n - 1) { c++; mbar_wait_bg(fullB + 8 * (c % NB), (c / NB) & 1); }
                mbar_arrive_cluster(emptyB + 8 * slot, 0);
                mbar_arrive_cluster(emptyB + 8 * slot, 1);
              }
              mbar_arrive(ackBar + 8 * w);
            }
            __syncwarp();
          }
          bar_sync(5 + w, 160);
          if (lane == 0) {
            mbar_arrive_rlx(ackBar + 8 * w);
            asm volatile("fence.proxy.async.global;\nfence.acq_rel.gpu;" ::: "memory");
            if (stores) red_relaxed(&g_kvflag[type == T_KV ? (code & 255) : 256 + park_slot(type, h) * 8 + rb], 1);
            else st_relaxed(&g_pflag[blk64_of(type, rb, rank, w)][(type == T_ATT ? 0 : NH) + h], get_epoch());
          }
          __syncwarp();
          cnt += nload + (stores ? 0 : (mode == M_MERGE ? 14 : 7));
        }
      }
    }
    __syncwarp();
    asm volatile("barrier.cluster.arrive.relaxed.aligned;" ::: "memory");
  } else {
    asm volatile("setmaxnreg.inc.sync.aligned.u32 232;");
    const int w = (warp >> 2) - 1, w4 = warp & 3, t128 = tid & 127;
    int sb = 0, pb = 0, sa = 0, pack_ = 1;
    float acc[128];
    uint32_t af[64];
    int pend = -1;
    auto advB = [&]() { if (++sb == NB) { sb = 0; pb ^= 1; } };
    auto advA = [&]() { sa = (sa + 1) & (NA - 1); };
    auto relB = [&](int s) { if (lane == 0 && w4 < 2) mbar_arrive_cluster(emptyB + 8 * s, w4); };
    auto relB2 = [&](int s) { if (lane == 0 && w4 >= 2) mbar_arrive_cluster(emptyB + 8 * s, w4 - 2); };
    auto relA = [&](int s) { if (t128 == 64) mbar_arrive_rlx(emptyA + 8 * s); };
    auto signal_done = [&]() {
      mbar_wait(ackBar + 8 * w, pack_);
      bar_arrive(5 + w, 160);
      pack_ ^= 1;
    };
    auto pack_acc = [&]() {
#pragma unroll
      for (int i = 0; i < 64; i++) af[i] = pack_bf16(acc[2 * i], acc[2 * i + 1]);
    };
    auto store_job = [&](auto PART) {
      uint4* dst = reinterpret_cast<uint4*>(g_kv + pend + (t128 >> 5) * 16 * KVW + (lane >> 2) * KVW) + (lane & 3);
#pragma unroll
      for (int v = decltype(PART)::value * 4; v < decltype(PART)::value * 4 + 4; v++) {
        const int b = (v >> 1) * 8 + (v & 1);
        dst[(v & 1) * KVW + (v >> 1) * 4] = make_uint4(af[b], af[b + 2], af[b + 4], af[b + 6]);
      }
    };
    auto silu2 = [](uint32_t gp, uint32_t up) { return mul_bf16x2(pack_bf16(silu_f(bf_lo(gp)), silu_f(bf_hi(gp))), up); };
    bool seen = false;
    auto kblock = [&](auto FIRST) {
      if (!decltype(FIRST)::value || !seen) mbar_wait(fullB + 8 * sb, pb);
      const uint32_t da = mkdesc(sA + sa * A_UNIT + w * 8192, 16);
      const uint32_t db = mkdesc(sB + sb * B_SLOT, 8192);
      wg_fence();
#pragma unroll
      for (int kk = 0; kk < 4; kk++) wgmma_ss_n256_t(acc, da + kk * 2, db + kk * 128, !(decltype(FIRST)::value && kk == 0));
      wg_commit();
    };

    int it = 0, pass = 0, next = sched[0];
#pragma unroll 1
    while ((next >> 14) != T_END) {
      kblock(IC<1>{});
      if (pend >= 0) store_job(IC<0>{});
      const int code = next, type = code >> 14;
      const bool again = type == T_FFN && pass == 0;
      if (!again) { it++; next = it < MAX_ITEMS ? sched[it] : T_END << 14; }
      const int rb = code & 7;
      const int mode = type == T_KV ? M_PARK : (code >> 12) & 3;
      const int dest = blk64_of(type, rb, rank, w) * 64 * KVW +
                       (type == T_KV ? (code & 0xf8) * 32 : 2 * NH * HD + park_slot(type, (code >> 3) & 15) * 256);
      {
        const int nkb = type == T_KV ? DC / 64 : DM / 64, hold = type == T_ATT ? NA : 0;
        int psa = sa, psb = sb;
        advA(); advB();
        for (int kb = 1; kb < nkb; kb++) {
          kblock(IC<0>{});
          wg_wait<1>();
          relB(psb); if (kb - 1 < nkb - hold) relA(psa);
          psa = sa; psb = sb;
          advA(); advB();
          if (pend >= 0) {
            if (kb == 1) store_job(IC<1>{});
            if (kb == 2) store_job(IC<2>{});
            if (kb == 3) { store_job(IC<3>{}); signal_done(); pend = -1; }
          }
          if (pass) {
#pragma unroll
            for (int part = 0; part < 5; part++)
              if (kb == part + 1) {
#pragma unroll
                for (int i = part * 32 / 5; i < (part + 1) * 32 / 5; i++) af[i] = silu2(af[i], af[32 + i]);
              }
          }
        }
        seen = again || (type != T_ATT && mode == M_PARK && (next >> 14) != T_END);
        if (seen) mbar_wait(fullB + 8 * sb, pb);
        wg_wait<0>();
        fence_regs(acc);
        relB(psb); if (hold == 0) relA(psa);
      }
      if (pass == 0) {
        pack_acc();
        if (again) { pass = 1; continue; }
        if (type == T_KV) { pend = dest; continue; }
      } else {
#pragma unroll
        for (int i = 0; i < 32; i++)
          af[32 + i] = silu2(pack_bf16(acc[2 * i], acc[2 * i + 1]), pack_bf16(acc[64 + 2 * i], acc[64 + 2 * i + 1]));
        pass = 0;
      }
      {
        if (type == T_ATT) {
          {
            const uint32_t qb = sA + w * 8192 + (w4 * 16 + (lane >> 2)) * 128;
#pragma unroll
            for (int v = 0; v < 16; v++) {
              const int b = (v >> 1) * 8 + (v & 1);
              asm volatile("st.shared.v4.b32 [%0], {%1, %2, %3, %4};"
                           :: "r"(qb + (v >> 2) * A_UNIT + (v & 1) * 1024 + (((((v >> 1) & 1) * 4 + (lane & 3)) ^ (lane >> 2)) << 4)),
                              "r"(af[b]), "r"(af[b + 2]), "r"(af[b + 4]), "r"(af[b + 6]) : "memory");
            }
            asm volatile("fence.proxy.async.shared::cta;" ::: "memory");
          }
          bar_sync(1 + w, 128);
          const int N = 4 * rb + 4;
          const int n = blk64_of(T_ATT, rb, rank, w) + 1;
          const float cs = 0.0625f * 1.4426950408889634f;
          float n0, n1, l0, l1;
          float S[32];
          uint32_t pf[16];
          const uint32_t dq = mkdesc(sA + w * 8192, 16);
          auto qk = [&](int slot) {
            const uint32_t dk = mkdesc(sB + slot * B_SLOT, 16);
#pragma unroll
            for (int kk = 0; kk < 16; kk++)
              wgmma_ss_n64_k(S, dq + (kk >> 2) * (A_UNIT >> 4) + (kk & 3) * 2, dk + (kk >> 2) * 512 + (kk & 3) * 2, kk != 0);
            wg_commit();
          };
          auto pv = [&](int slot, int accum) {
            const uint32_t dv = mkdesc(sB + slot * B_SLOT, 8192);
#pragma unroll
            for (int kk = 0; kk < 4; kk++)
              wgmma_rs_n256_t(acc, pf[4 * kk], pf[4 * kk + 1], pf[4 * kk + 2], pf[4 * kk + 3], dv + kk * 128, accum | kk);
            wg_commit();
          };
          uint32_t pn[16];
          float r0, r1;
          auto mask_diag = [&]() {
            if (lane == 0) mbar_arrive_rlx(emptyA + 8 * w4);
            if (n < N) signal_done();
            const int rr = w4 * 16 + (lane >> 2), cc = (lane & 3) * 2;
#pragma unroll
            for (int i = 0; i < 8; i++) {
              if (8 * i + cc > rr) S[4 * i] = -INFINITY;
              if (8 * i + cc + 1 > rr) S[4 * i + 1] = -INFINITY;
              if (8 * i + cc > rr + 8) S[4 * i + 2] = -INFINITY;
              if (8 * i + cc + 1 > rr + 8) S[4 * i + 3] = -INFINITY;
            }
          };
          auto exps = [&](float mul, float a0, float a1) {
#pragma unroll
            for (int i = 0; i < 8; i++) {
              S[4 * i] = fmaf(S[4 * i], mul, a0); S[4 * i + 1] = fmaf(S[4 * i + 1], mul, a0);
              S[4 * i + 2] = fmaf(S[4 * i + 2], mul, a1); S[4 * i + 3] = fmaf(S[4 * i + 3], mul, a1);
            }
            float e[2][4];
            float r0a = 0.f, r1a = 0.f, r0b = 0.f, r1b = 0.f;
#pragma unroll
            for (int i = 0; i <= 8; i++) {
              if (i < 8) {
#pragma unroll
                for (int q = 0; q < 4; q++) asm volatile("ex2.approx.ftz.f32 %0, %1;" : "=f"(e[i & 1][q]) : "f"(S[4 * i + q]));
              }
              if (i > 0) {
                const float* p = e[(i - 1) & 1];
                asm volatile("add.f32 %0, %0, %1;" : "+f"(r0a) : "f"(p[0]));
                asm volatile("add.f32 %0, %0, %1;" : "+f"(r0b) : "f"(p[1]));
                asm volatile("cvt.rn.bf16x2.f32 %0, %1, %2;" : "=r"(pn[2 * i - 2]) : "f"(p[1]), "f"(p[0]));
                asm volatile("add.f32 %0, %0, %1;" : "+f"(r1a) : "f"(p[2]));
                asm volatile("add.f32 %0, %0, %1;" : "+f"(r1b) : "f"(p[3]));
                asm volatile("cvt.rn.bf16x2.f32 %0, %1, %2;" : "=r"(pn[2 * i - 1]) : "f"(p[3]), "f"(p[2]));
              }
            }
            r0 = r0a + r0b; r1 = r1a + r1b;
          };
          auto row_max = [&](float& x0, float& x1) {
            float a0 = fmaxf(fmaxf(S[0], S[1]), fmaxf(S[4], S[5])), a1 = fmaxf(fmaxf(S[2], S[3]), fmaxf(S[6], S[7]));
            float b0 = fmaxf(fmaxf(S[8], S[9]), fmaxf(S[12], S[13])), b1 = fmaxf(fmaxf(S[10], S[11]), fmaxf(S[14], S[15]));
            float c0 = fmaxf(fmaxf(S[16], S[17]), fmaxf(S[20], S[21])), c1 = fmaxf(fmaxf(S[18], S[19]), fmaxf(S[22], S[23]));
            float d0 = fmaxf(fmaxf(S[24], S[25]), fmaxf(S[28], S[29])), d1 = fmaxf(fmaxf(S[26], S[27]), fmaxf(S[30], S[31]));
            x0 = fmaxf(fmaxf(a0, b0), fmaxf(c0, d0)); x1 = fmaxf(fmaxf(a1, b1), fmaxf(c1, d1));
            x0 = fmaxf(x0, __shfl_xor_sync(0xffffffffu, x0, 1));
            x1 = fmaxf(x1, __shfl_xor_sync(0xffffffffu, x1, 1));
            x0 = fmaxf(x0, __shfl_xor_sync(0xffffffffu, x0, 2));
            x1 = fmaxf(x1, __shfl_xor_sync(0xffffffffu, x1, 2));
          };
          {
            mbar_wait(fullB + 8 * sb, pb);
            wg_fence();
            qk(sb);
            const int sk = sb; advB();
            if (n > 1) mbar_wait(fullB + 8 * sb, pb);
            wg_wait<0>();
            fence_regs(S);
            relB(sk);
            if (n == 1) mask_diag();
            row_max(n0, n1);
            n0 *= -cs; n1 *= -cs;
            exps(cs, n0, n1);
            l0 = r0; l1 = r1;
#pragma unroll
            for (int i = 0; i < 16; i++) asm volatile("mov.b32 %0, %1;" : "=r"(pf[i]) : "r"(pn[i]));
          }
          int sv;
          auto step = [&](int t, bool diag) -> bool {
            const int sk = sb; advB();
            sv = sb;
            mbar_wait(fullB + 8 * sb, pb);
            advB();
            wg_fence();
            qk(sk);
            pv(sv, t > 1);
            wg_wait<1>();
            fence_regs(S);
            relB(sk);
            if (!diag) mbar_wait(fullB + 8 * sb, pb);
            if (diag) mask_diag();
            exps(cs, n0, n1);
            const bool resc = __any_sync(0xffffffffu, !(r0 <= 4096.f && r1 <= 4096.f));
            return resc;
          };
          auto finish_pv = [&]() {
            wg_wait<0>();
            fence_regs(acc);
            relB2(sv);
          };
          auto commit_p = [&]() {
            l0 += r0; l1 += r1;
#pragma unroll
            for (int i = 0; i < 16; i++) asm volatile("mov.b32 %0, %1;" : "=r"(pf[i]) : "r"(pn[i]));
          };
          for (int t = 1; t < n; t++) {
            bool resc = false;
            for (; t < n - 1; t++) {
              resc = step(t, false);
              if (resc) break;
              finish_pv();
              commit_p();
            }
            if (!resc) resc = step(t, true);
            finish_pv();
            if (resc) {
              float d0, d1;
              row_max(d0, d1);
              d0 = -fmaxf(d0, 0.f); d1 = -fmaxf(d1, 0.f);
              n0 += d0; n1 += d1;
              const float sc0 = ex2(d0), sc1 = ex2(d1);
              l0 *= sc0; l1 *= sc1;
              exps(1.0f, d0, d1);
#pragma unroll
              for (int i = 0; i < 32; i++) {
                acc[4 * i] *= sc0; acc[4 * i + 1] *= sc0; acc[4 * i + 2] *= sc1; acc[4 * i + 3] *= sc1;
              }
            }
            commit_p();
          }
          {
            if (n < N) advB();
            mbar_wait(fullB + 8 * sb, pb);
            wg_fence();
            pv(sb, n > 1);
            wg_wait<0>();
            fence_regs(acc);
            relB(sb); advB();
          }
          l0 += __shfl_xor_sync(0xffffffffu, l0, 1); l1 += __shfl_xor_sync(0xffffffffu, l1, 1);
          l0 += __shfl_xor_sync(0xffffffffu, l0, 2); l1 += __shfl_xor_sync(0xffffffffu, l1, 2);
          const float i0 = rcp(l0), i1 = rcp(l1);
#pragma unroll
          for (int i = 0; i < 32; i++) {
            af[2 * i] = pack_bf16(acc[4 * i] * i0, acc[4 * i + 1] * i0);
            af[2 * i + 1] = pack_bf16(acc[4 * i + 2] * i1, acc[4 * i + 3] * i1);
          }
          if (n < N) mbar_wait(ackBar + 8 * w, pack_);
          for (int r = 2 * (N - n) - 1; r > 0; r--) advB();
        }
        if (mode == M_PARK) {
          pend = dest;
        } else {
          uint4* dst = &g_part[(type == T_ATT ? 0 : NH) + ((code >> 3) & 15)][((blk64_of(type, rb, rank, w) * 4 + w4) * NV4) * 32 + lane];
          auto project = [&](auto MG) {
            constexpr bool merge = decltype(MG)::value;
            int psb = -1;
            auto half = [&](auto& o, auto SRC, auto FIRST) {
              constexpr bool wide = sizeof(o) == 256;
#pragma unroll
              for (int kb = 0; kb < 4; kb++) {
                const bool newslot = wide ? (kb & 1) == 0 : kb == 0;
                if (newslot) { mbar_wait(fullB + 8 * sb, pb); }
                const uint32_t db = mkdesc(sB + sb * B_SLOT + (wide ? (kb & 1) * 16384 : kb * 8192), 8192);
                const uint32_t da = mkdesc(sA + ((sa + kb) & (NA - 1)) * A_UNIT + w * 8192, 16);
                wg_fence();
#pragma unroll
                for (int kk = 0; kk < 4; kk++) {
                  const int a = 16 * kb + 4 * kk;
                  const int sd = !(decltype(FIRST)::value && (kb | kk) == 0);
                  if constexpr (decltype(SRC)::value == 0) {
                    if constexpr (wide) wgmma_rs_n128_t(o, af[a], af[a + 1], af[a + 2], af[a + 3], db + kk * 128, sd);
                    else wgmma_rs_n64_t(o, af[a], af[a + 1], af[a + 2], af[a + 3], db + kk * 128, sd);
                  } else {
                    if constexpr (wide) wgmma_ss_n128_t(o, da + kk * 2, db + kk * 128, sd);
                    else wgmma_ss_n64_t(o, da + kk * 2, db + kk * 128, sd);
                  }
                }
                wg_commit();
                if (newslot && !(decltype(FIRST)::value && kb == 0)) {
                  wg_wait<1>();
                  relB(psb);
                  if constexpr (!wide && merge) { if (lane == 0) mbar_arrive_rlx(emptyA + 8 * w4); }
                }
                if (wide ? (kb & 1) == 1 : kb == 3) { psb = sb; advB(); }
              }
            };
            auto flush = [&](auto& o) {
              wg_wait<0>();
              fence_regs(o);
              relB(psb);
#pragma unroll
              for (int v = 0; v < (int)sizeof(o) / 32; v++)
                dst[v * 32] = make_uint4(pack_bf16(o[8 * v], o[8 * v + 1]), pack_bf16(o[8 * v + 2], o[8 * v + 3]),
                                         pack_bf16(o[8 * v + 4], o[8 * v + 5]), pack_bf16(o[8 * v + 6], o[8 * v + 7]));
            };
#pragma unroll 1
            for (int c = 0; c < 3; c++) {
              float o[64];
              half(o, IC<0>{}, IC<1>{});
              if constexpr (merge) half(o, IC<1>{}, IC<0>{});
              flush(o);
              dst += 8 * 32;
            }
            float o[32];
            if constexpr (merge) half(o, IC<1>{}, IC<1>{});
            half(o, IC<0>{}, IC<!merge>{});
            flush(o);
          };
          if (mode == M_MERGE) project(IC<1>{}); else project(IC<0>{});
          signal_done();
        }
      }
    }

    if (pend >= 0) { store_job(IC<0>{}); store_job(IC<1>{}); store_job(IC<2>{}); store_job(IC<3>{}); signal_done(); }
    int cph = 0;
    for (int slice = blockIdx.x; slice < 128; slice += gridDim.x, cph ^= 1) {
      if (slice != blockIdx.x) {
        bar_sync(9, 256);
        for (int i = 0; i < 3; i++) { relB(sb); advB(); }
        if (lane == 0) mbar_arrive_rlx(emptyA + 8 * w4);
      }
      if (warp == 11) continue;
      auto operand = [&](int at) {
        const int sl = sb + (at >> 1);
        return at >= 6 ? sA + ((sa + at - 6) & (NA - 1)) * A_UNIT : sB + (sl >= NB ? sl - NB : sl) * B_SLOT + (at & 1) * (NV4 * 512);
      };
      const int t224 = tid - 128;
      const int lo = ((lane >> 2) + (lane & 1) * 8) * DM + (t224 >> 5) * 16 + (lane & 2) * 4, go = slice * 16 * DM + lo;
#pragma unroll 1
      for (int pass = 0; pass < 2; pass++) {
        float sum[32];
#pragma unroll
        for (int i = 0; i < 32; i++) sum[i] = 0.f;
#pragma unroll 1
        for (int at = pass ? 0 : NCMB - 1; at < NCMB; at++) {
          if (pass) mbar_wait(cmbBar + 8 * at, cph);
          if (at < 2) continue;
#pragma unroll
          for (int k = 0; k < 4; k++) {
            uint4 v;
            asm volatile("ld.shared.v4.u32 {%0, %1, %2, %3}, [%4];" : "=r"(v.x), "=r"(v.y), "=r"(v.z), "=r"(v.w)
                         : "r"(operand(at) + (t224 + 224 * k) * 16) : "memory");
            sum[8 * k] += bf_lo(v.x); sum[8 * k + 1] += bf_hi(v.x); sum[8 * k + 2] += bf_lo(v.y); sum[8 * k + 3] += bf_hi(v.y);
            sum[8 * k + 4] += bf_lo(v.z); sum[8 * k + 5] += bf_hi(v.z); sum[8 * k + 6] += bf_lo(v.w); sum[8 * k + 7] += bf_hi(v.w);
          }
        }
#pragma unroll
        for (int k = 0; k < 4; k++) {
          uint32_t g[4];
          asm volatile("ld.shared.v4.u32 {%0, %1, %2, %3}, [%4];" : "=r"(g[0]), "=r"(g[1]), "=r"(g[2]), "=r"(g[3])
                       : "r"(operand(0) + (t224 + 224 * k) * 16) : "memory");
          uint32_t t[4];
#pragma unroll
          for (int q = 0; q < 4; q++) t[q] = mul_bf16x2(pack_bf16(sum[8 * k + 2 * q], sum[8 * k + 2 * q + 1]), g[q]);
#pragma unroll
          for (int d = 1; d <= 2; d <<= 1) {
            const bool up = lane & d;
#pragma unroll
            for (int q = 0; q < 4; q++)
              if (!(q & d)) {
                const uint32_t give = up ? t[q] : t[q | d];
                const uint32_t got = __shfl_xor_sync(0xffffffffu, give, d);
                if (up) t[q] = got; else t[q | d] = got;
              }
          }
          uint32_t xv[4];
          asm volatile("ld.shared.v4.u32 {%0, %1, %2, %3}, [%4];" : "=r"(xv[0]), "=r"(xv[1]), "=r"(xv[2]), "=r"(xv[3])
                       : "r"(operand(1) + (lo + k * 112) * 2) : "memory");
          asm volatile("{\n.reg .pred p;\nsetp.ne.b32 p, %5, 0;\n@p st.global.v4.b32 [%0], {%1, %2, %3, %4};\n}\n"
                       :: "l"(P.out + go + k * 112), "r"(add_bf16x2(xv[0], t[0])), "r"(add_bf16x2(xv[1], t[1])),
                          "r"(add_bf16x2(xv[2], t[2])), "r"(add_bf16x2(xv[3], t[3])), "r"(pass) : "memory");
        }
      }
    }
  }
  if (warp >= 4) asm volatile("barrier.cluster.arrive.relaxed.aligned;" ::: "memory");
  __syncwarp();
  asm volatile("barrier.cluster.wait.aligned;" ::: "memory");
}

typedef CUresult (*EncodeFn)(CUtensorMap*, CUtensorMapDataType, cuuint32_t, void*, const cuuint64_t*, const cuuint64_t*,
                             const cuuint32_t*, const cuuint32_t*, CUtensorMapInterleave, CUtensorMapSwizzle,
                             CUtensorMapL2promotion, CUtensorMapFloatOOBfill);

void make_map(EncodeFn fn, CUtensorMap* tm, const void* ptr, int rows, int cols, int box_rows) {
  cuuint64_t dims[2] = {(cuuint64_t)cols, (cuuint64_t)rows};
  cuuint64_t strides[1] = {(cuuint64_t)cols * 2};
  cuuint32_t box[2] = {64, (cuuint32_t)box_rows};
  cuuint32_t es[2] = {1, 1};
  fn(tm, CU_TENSOR_MAP_DATA_TYPE_BFLOAT16, 2, const_cast<void*>(ptr), dims, strides, box, es, CU_TENSOR_MAP_INTERLEAVE_NONE,
     CU_TENSOR_MAP_SWIZZLE_128B, CU_TENSOR_MAP_L2_PROMOTION_L2_256B, CU_TENSOR_MAP_FLOAT_OOB_FILL_NONE);
}

void make_proj_map(EncodeFn fn, CUtensorMap* tm, const void* ptr, int rows, bool perm) {
  cuuint64_t dims[5] = {(cuuint64_t)DM, 2, 4, 4, (cuuint64_t)rows / 32};
  cuuint64_t strides[4] = {DM * 2, (cuuint64_t)DM * 2 * (perm ? 8 : 2), (cuuint64_t)DM * 2 * (perm ? 2 : 8), DM * 2 * 32};
  cuuint32_t box[5] = {64, 2, 4, 4, 2};
  cuuint32_t es[5] = {1, 1, 1, 1, 1};
  fn(tm, CU_TENSOR_MAP_DATA_TYPE_BFLOAT16, 5, const_cast<void*>(ptr), dims, strides, box, es, CU_TENSOR_MAP_INTERLEAVE_NONE,
     CU_TENSOR_MAP_SWIZZLE_128B, CU_TENSOR_MAP_L2_PROMOTION_L2_256B, CU_TENSOR_MAP_FLOAT_OOB_FILL_NONE);
}

const uint16_t kSched66[MAX_CL][9] = {
  {0x0000,0x9001,0x0098,0x5002,0x001c,0x005d,0x603d,0xc000,0xc000},
  {0x0080,0x0061,0x0099,0x5021,0x00f6,0x004d,0x606e,0xc000,0xc000},
  {0x0001,0x9002,0x0019,0x00e8,0x5016,0x007f,0x6069,0xc000,0xc000},
  {0x0081,0x00e1,0x001a,0x00e9,0x5026,0x00ff,0x6079,0xc000,0xc000},
  {0x0002,0x0062,0x009a,0x006a,0x5023,0x00fc,0x606c,0xc000,0xc000},
  {0x0082,0x00e2,0x9020,0x0069,0x0075,0x5044,0x605b,0xc000,0xc000},
  {0x0003,0x0063,0xa009,0x0065,0x000e,0x004f,0x600d,0xc000,0xc000},
  {0x0083,0x00e3,0xa00a,0x00e5,0x008e,0x00cf,0x00fe,0x606b,0xc000},
  {0x0010,0x0024,0x001b,0x00ea,0x5007,0x600a,0xc000,0xc000,0xc000},
  {0x0090,0x8031,0x00db,0x00f9,0x00f7,0x5066,0x6038,0xc000,0xc000},
  {0x0011,0x00a4,0x009b,0x006b,0x5031,0x00cd,0x5033,0x6009,0xc000},
  {0x0091,0x0025,0x0028,0x5013,0x004c,0x600e,0xc000,0xc000,0xc000},
  {0x0012,0x00a5,0x00a8,0x00eb,0x5036,0x602b,0xc000,0xc000,0xc000},
  {0x0092,0x0026,0x9021,0x5025,0x007c,0x603c,0xc000,0xc000,0xc000},
  {0x0013,0x9003,0x8033,0x007a,0x000c,0x5064,0x601a,0xc000,0xc000},
  {0x0093,0x00a6,0x0029,0x0054,0x00f5,0x5054,0x5070,0x6029,0xc000},
  {0x0020,0x0027,0x00a9,0x00d4,0x0076,0x003f,0x5061,0x5072,0x6078},
  {0x00a0,0x00a7,0x002a,0xa00f,0x000f,0x005c,0x601d,0xc000,0xc000},
  {0x0021,0x0034,0x00aa,0x0055,0x5017,0x602a,0xc000,0xc000,0xc000},
  {0x00a1,0x00b4,0x9022,0x5012,0x002c,0x602f,0xc000,0xc000,0xc000},
  {0x0022,0x0035,0x002b,0x00d5,0x5046,0x603b,0xc000,0xc000,0xc000},
  {0x00a2,0x00b5,0xa00b,0x0066,0x008f,0x00dc,0x602d,0xc000,0xc000},
  {0x0023,0x0036,0x00ab,0x0056,0x5055,0x605c,0xc000,0xc000,0xc000},
  {0x00a3,0x00b6,0x8034,0x007b,0x000d,0x5050,0x603e,0xc000,0xc000},
  {0x0030,0x0037,0x5004,0x009c,0x00dd,0x604d,0xc000,0xc000,0xc000},
  {0x00b0,0x9004,0xa00c,0x00e6,0x001d,0x005e,0x605d,0xc000,0xc000},
  {0x0031,0x9005,0x0038,0x5006,0x007e,0x604b,0xc000,0xc000,0xc000},
  {0x00b1,0x00b7,0x0039,0x0057,0x5037,0x606a,0xc000,0xc000,0xc000},
  {0x0032,0x9006,0x00b8,0x00d6,0x5027,0x604a,0xc000,0xc000,0xc000},
  {0x00b2,0x0044,0x00b9,0x00d7,0x5047,0x607a,0xc000,0xc000,0xc000},
  {0x0033,0x00c4,0x003a,0x5020,0x5024,0x00fd,0x600b,0xc000,0xc000},
  {0x00b3,0x0045,0x9023,0x5010,0x0074,0x003e,0x5075,0x6058,0xc000},
  {0x0040,0x8032,0x0068,0x00fb,0x5034,0x602c,0xc000,0xc000,0xc000},
  {0x00c0,0x00c5,0x5005,0x00bf,0x007d,0x607c,0xc000,0xc000,0xc000},
  {0x0041,0x0046,0x00ba,0xa019,0x001e,0x005f,0x5043,0x6008,0xc000},
  {0x00c1,0x9007,0x9024,0xa018,0x009d,0x00de,0x606d,0xc000,0xc000},
  {0x0042,0x00c6,0x003b,0xa01a,0x009e,0x00df,0x607d,0xc000,0xc000},
  {0x00c2,0x0047,0x0048,0x0078,0x5056,0x607b,0xc000,0xc000,0xc000},
  {0x0043,0x00c7,0x5001,0x0079,0x0077,0x004e,0x5052,0x605a,0xc000},
  {0x00c3,0x9010,0x00bb,0xa01b,0x001f,0x600f,0xc000,0xc000,0xc000},
  {0x0004,0x0070,0x00c8,0x8037,0x5057,0x6049,0xc000,0xc000,0xc000},
  {0x0084,0x00f0,0x9025,0xa01c,0x009f,0x601f,0xc000,0xc000,0xc000},
  {0x0005,0x0071,0x5015,0x00cc,0x601e,0xc000,0xc000,0xc000,0xc000},
  {0x0085,0x00f1,0x00c9,0xa01e,0x002d,0x006c,0x5060,0x601b,0xc000},
  {0x0006,0x9011,0x8035,0x0064,0x5067,0x6059,0xc000,0xc000,0xc000},
  {0x0086,0x9012,0x0049,0xa01d,0x00ac,0x603f,0xc000,0xc000,0xc000},
  {0x0007,0x9013,0x004a,0xa01f,0x00ad,0x00ec,0x5053,0x6028,0xc000},
  {0x0087,0x9014,0x8036,0x00e4,0x008d,0x00ce,0x607e,0xc000,0xc000},
  {0x0014,0x0072,0x00ca,0x5035,0x604e,0xc000,0xc000,0xc000,0xc000},
  {0x0094,0x00f2,0x004b,0x5045,0x605e,0xc000,0xc000,0xc000,0xc000},
  {0x0015,0x0073,0xa00e,0x00e7,0x002f,0x605f,0xc000,0xc000,0xc000},
  {0x0095,0x9015,0xa00d,0x0067,0x00ae,0x604f,0xc000,0xc000,0xc000},
  {0x0016,0x00f3,0x5011,0x00fa,0x008c,0x5042,0x604c,0xc000,0xc000},
  {0x0096,0x9016,0x9026,0xa028,0x002e,0x006d,0x5062,0x6039,0xc000},
  {0x0017,0x0008,0x00cb,0xa029,0x00af,0x606f,0xc000,0xc000,0xc000},
  {0x0097,0x0088,0x0058,0xa02a,0x5041,0x00ef,0x601c,0xc000,0xc000},
  {0x0050,0x0009,0x5003,0x5032,0x006f,0x600c,0xc000,0xc000,0xc000},
  {0x00d0,0x0089,0x00d8,0x00f8,0x5040,0x00be,0x607f,0xc000,0xc000},
  {0x0051,0x000a,0x0059,0xa02b,0x003c,0x006e,0x5071,0x603a,0xc000},
  {0x00d1,0x008a,0x00d9,0x5030,0x00f4,0x5051,0x602e,0xc000,0xc000},
  {0x0052,0x9017,0x9027,0x5014,0x00ed,0x5063,0x6048,0xc000,0xc000},
  {0x00d2,0x000b,0x005a,0xa02c,0x00bc,0x00ee,0x5073,0x6068,0xc000},
  {0x0053,0x008b,0x00da,0xa02d,0x003d,0x5074,0x6019,0xc000,0xc000},
  {0x00d3,0x0018,0x005b,0xa02e,0x00bd,0x5065,0x6018,0xc000,0xc000},
  {0x0060,0x9000,0xa008,0x5022,0x5076,0xc000,0xc000,0xc000,0xc000},
  {0x00e0,0x8030,0x5000,0xa02f,0x5077,0xc000,0xc000,0xc000,0xc000},
};

void build_schedule(uint16_t (*sched)[MAX_ITEMS], int ncl) {
  for (int c = 0; c < MAX_CL; c++) for (int i = 0; i < MAX_ITEMS; i++) sched[c][i] = (uint16_t)(T_END << 14);
  if (ncl == MAX_CL) {
    for (int c = 0; c < MAX_CL; c++) for (int i = 0; i < 9; i++) sched[c][i] = kSched66[c][i];
    return;
  }
  double load[MAX_CL] = {};
  int cnt[MAX_CL] = {};
  auto put = [&](int code, double cost) {
    int best = -1;
    for (int c = 0; c < ncl; c++) if (cnt[c] < MAX_ITEMS && (best < 0 || load[c] < load[best] - 1e-9)) best = c;
    sched[best][cnt[best]++] = (uint16_t)code; load[best] += cost;
  };
  for (int i = 0; i < 256; i++) put((T_KV << 14) | ((i & 1) << 7) | (i >> 1), 18.5);
  for (int rb = 0; rb < 8; rb++) for (int c = 0; c < 7; c += 2) put((T_FFN << 14) | ((c < 6 ? M_PARK : M_SINGLE) << 12) | (c << 3) | rb, c < 6 ? 21.0 : 29.0);
  for (int rb = 0; rb < 8; rb++) for (int c = 1; c < 7; c += 2) put((T_FFN << 14) | (M_MERGE << 12) | (c << 3) | rb, 36.0);
  for (int m = 0; m < 2; m++)
    for (int j = 7; j >= 0; j--)
      for (int h = m; h < NH; h += 2) put((T_ATT << 14) | ((m ? M_MERGE : M_PARK) << 12) | (h << 3) | j, (m ? 32.0 : 18.0) + 8.3 * j);
}


}


extern "C" void kernel_launch(void* const* d_in, const int* in_sizes, int n_in, void* d_out, int out_size) {
  static Params P;
  static int ncl = 0;
  static const void* cached[11] = {};
  bool same = ncl != 0 && cached[10] == d_out;
  for (int i = 0; i < 10 && same; i++) same = cached[i] == d_in[i];
  if (!same) {
    void* fnp = nullptr;
    cudaDriverEntryPointQueryResult qr;
    cudaGetDriverEntryPoint("cuTensorMapEncodeTiled", &fnp, cudaEnableDefault, &qr);
    EncodeFn fn = (EncodeFn)fnp;
    void *kv, *xn;
    cudaGetSymbolAddress(&kv, g_kv);
    cudaGetSymbolAddress(&xn, g_xn);
    make_map(fn, &P.tm_ckv, d_in[1], SEQ, DC, 64);
    make_map(fn, &P.tm_wq, d_in[2], DM, NH * HD, 64);
    make_map(fn, &P.tm_wuk, d_in[3], DC, NH * HD, 64);
    make_map(fn, &P.tm_wuv, d_in[4], DC, NH * HD, 64);
    make_proj_map(fn, &P.tm_proj[0], d_in[5], NH * HD, false);
    make_proj_map(fn, &P.tm_proj[1], d_in[5], NH * HD, true);
    make_map(fn, &P.tm_wg, d_in[7], DM, FF, 64);
    make_map(fn, &P.tm_wu, d_in[8], DM, FF, 64);
    make_proj_map(fn, &P.tm_proj[2], d_in[9], FF, false);
    make_proj_map(fn, &P.tm_proj[3], d_in[9], FF, true);
    make_map(fn, &P.tm_kv, kv, SEQ, KVW, 64);
    make_map(fn, &P.tm_xn, xn, SEQ, DM, 64);
    P.x = (const __nv_bfloat16*)d_in[0];
    P.out = (__nv_bfloat16*)d_out;
    cudaFuncSetAttribute(fused_kernel, cudaFuncAttributeMaxDynamicSharedMemorySize, SMEM_BYTES);
    cudaLaunchConfig_t cfg = {};
    cfg.gridDim = dim3(2 * MAX_CL); cfg.blockDim = dim3(384); cfg.dynamicSmemBytes = SMEM_BYTES;
    int maxcl = 0;
    cudaOccupancyMaxActiveClusters(&maxcl, fused_kernel, &cfg);
    ncl = maxcl < MAX_CL ? maxcl : MAX_CL;
    if (ncl < 40) ncl = 40;
    build_schedule(P.sched, ncl);
    for (int i = 0; i < 10; i++) cached[i] = d_in[i];
    cached[10] = d_out;
  }
  fused_kernel<<<2 * ncl, 384, SMEM_BYTES, cudaStreamPerThread>>>(P);
}
```
